```python
import torch

def _softmax(x, axis=-1):
    return torch.softmax(x, dim=axis)
def _gelu(x):
    return torch.nn.functional.gelu(x, approximate="tanh")
def _silu(x):
    return torch.nn.functional.silu(x)
def _sigmoid(x):
    return torch.sigmoid(x)
def _layernorm(x, axis=-1, eps=1e-5):
    m = x.mean(dim=axis, keepdim=True)
    v = x.var(dim=axis, keepdim=True, unbiased=False)
    return (x - m) / torch.sqrt(v + eps)
def _scatter_add(tgt, idx, src, axis=0):
    return tgt.clone().index_add_(axis, idx, src)
def _segment_sum(src, seg, n):
    out = torch.zeros((n,) + src.shape[1:], dtype=src.dtype)
    return out.index_add_(0, seg, src)
def _pad(x, pw):
    flat = tuple(v for pair in reversed(pw) for v in pair)
    return torch.nn.functional.pad(x, flat)

kernel_name = 'concat_heads__grouped_kv_mqa__linear_attn_block__prompt'

def setup_inputs():

    _w = (lambda a: (lambda t: t.to(torch.bfloat16) if t.is_floating_point() else t)(torch.as_tensor(a)))
    def _A_setup():
        B, S, D, H = 1, 2048, 640, 32
        Dh = D // H
        return {
            "x": _w((lambda *s: torch.randn(*s, dtype=torch.bfloat16) * 0.05)(B, S, D)),
            "wq": _w((lambda *s: torch.randn(*s, dtype=torch.bfloat16) * 0.8)(D, H * Dh)),
            "wk": _w((lambda *s: torch.randn(*s, dtype=torch.bfloat16) * 0.8)(D, Dh)),
            "wv": _w((lambda *s: torch.randn(*s, dtype=torch.bfloat16) * 0.05)(D, Dh)),
            "wo": _w((lambda *s: torch.randn(*s, dtype=torch.bfloat16) * 0.05)(H * Dh, D)),
        }
    _A_in = _A_setup()

    def _B_setup():
        B, S, D = 1, 2048, 640
        return {
            "x": _w((lambda *s: torch.randn(*s, dtype=torch.bfloat16) * 0.05)(B, S, D)),
            "wqkv": _w((lambda *s: torch.randn(*s, dtype=torch.bfloat16) * 0.4)(D, 3 * D)),
            "wo": _w((lambda *s: torch.randn(*s, dtype=torch.bfloat16) * 0.05)(D, D)),
        }
    _B_in = _B_setup()

    return {
        "A_x": _A_in["x"],
        "A_wq": _A_in["wq"],
        "A_wk": _A_in["wk"],
        "A_wv": _A_in["wv"],
        "A_wo": _A_in["wo"],
        "B_x": _B_in["x"],
        "B_wqkv": _B_in["wqkv"],
        "B_wo": _B_in["wo"],
    }

def reference(A_x, A_wq, A_wk, A_wv, A_wo, B_x, B_wqkv, B_wo):
    def _A_ref(x, wq, wk, wv, wo):
        B, S, D = x.shape
        H = 32
        Dh = D // H
        q = (lambda x, *d: x.permute(*d))((x @ wq).reshape(B, S, H, Dh), 0, 2, 1, 3)
        k = x @ wk
        v = x @ wv
        scores = torch.einsum("bhqd,bkd->bhqk", q, k) * (Dh ** -0.5)
        p = _softmax(scores, axis=-1)
        o = torch.einsum("bhqk,bkd->bhqd", p, v)
        return (lambda x, *d: x.permute(*d))(o, 0, 2, 1, 3).reshape(B, S, H * Dh) @ wo

    def _B_ref(x, wqkv, wo):
        B, S, D = x.shape
        H = 32; Dh = D // H
        qkv = (lambda x, *d: x.permute(*d))((x @ wqkv).reshape(B, S, 3, H, Dh), 2, 0, 3, 1, 4)
        q, k, v = qkv[0], qkv[1], qkv[2]
        phi = lambda t: torch.where(t > 0, t + 1, torch.exp(t)) + 1e-6
        pq, pk = phi(q), phi(k)
        kv = torch.einsum("bhsd,bhse->bhde", pk, v)
        z = torch.einsum("bhsd->bhd", pk)
        num = torch.einsum("bhqd,bhde->bhqe", pq, kv)
        den = torch.einsum("bhqd,bhd->bhq", pq, z)[..., None] + 1e-6
        o = num / den
        return (lambda x, *d: x.permute(*d))(o, 0, 2, 1, 3).reshape(B, S, D) @ wo

    a = _A_ref(A_x, A_wq, A_wk, A_wv, A_wo)
    b = _B_ref(B_x, B_wqkv, B_wo)
    return torch.concatenate([a, b], axis=-1)
```

```cpp
#include <cuda_runtime.h>
#include <cuda_bf16.h>
#include <cuda.h>
#include <stdint.h>

typedef __nv_bfloat16 bf16;

__device__ __align__(1024) uint8_t g_Q[2 * 128 * 80 * 256];
__device__ __align__(1024) uint8_t g_KV[32 * 6144];
__device__ __align__(128) uint32_t g_stat[64];
__device__ __align__(16) float g_kvp[16 * 32 * 480];
__device__ __align__(16) float g_zp[16 * 640];
__device__ __align__(1024) bf16 g_M[640 * 640];
__device__ __align__(1024) uint8_t g_A[16 * 80 * 2048];
__device__ __align__(128) uint32_t g_F[2048 * 32];

enum { C_Q = 0, C_KV = 64, C_B = 65, C_M = 66, C_F = 67, C_DONE = 68, C_O1 = 69, C_O2 = 85, C_N = 101 };
__device__ __align__(128) uint32_t g_cnt[C_N * 32];

#define SAFE_BOUND 48.0f
#define MUFU_OFF 0x3B493FCBu
#define QSCALE (0.22360679774997896f * 1.4426950408889634f)

__device__ __forceinline__ uint32_t smem_u32(const void* p) { return (uint32_t)__cvta_generic_to_shared(p); }
__device__ __forceinline__ void mbar_init(uint32_t bar, uint32_t cnt) { asm volatile("mbarrier.init.shared::cta.b64 [%0], %1;" :: "r"(bar), "r"(cnt) : "memory"); }
__device__ __forceinline__ void mbar_expect(uint32_t bar, uint32_t bytes) { asm volatile("mbarrier.arrive.expect_tx.shared::cta.b64 _, [%0], %1;" :: "r"(bar), "r"(bytes) : "memory"); }
__device__ __forceinline__ void mbar_arrive(uint32_t bar) { asm volatile("mbarrier.arrive.shared::cta.b64 _, [%0];" :: "r"(bar) : "memory"); }
__device__ __forceinline__ void mbar_arrive_remote(uint32_t bar, uint32_t cta) {
    asm volatile("{.reg .b32 ra; mapa.shared::cluster.u32 ra, %0, %1; mbarrier.arrive.shared::cluster.b64 _, [ra];}" :: "r"(bar), "r"(cta) : "memory");
}
__device__ __forceinline__ void mbar_wait(uint32_t bar, uint32_t parity) {
    asm volatile("{\n.reg .pred p;\n.reg .u32 i;\nmov.u32 i, 0;\nW_LOOP:\nmbarrier.try_wait.parity.shared::cta.b64 p, [%0], %1;\n@p bra W_DONE;\n"
                 "add.u32 i, i, 1;\nsetp.lt.u32 p, i, 4194304;\n@p bra W_LOOP;\ntrap;\nW_DONE:\n}" :: "r"(bar), "r"(parity) : "memory");
}
__device__ __forceinline__ void fence_async_smem() { asm volatile("fence.proxy.async.shared::cta;" ::: "memory"); }
__device__ __forceinline__ void fence_mbar_init() { asm volatile("fence.mbarrier_init.release.cluster;" ::: "memory"); }
__device__ __forceinline__ void cluster_sync() { asm volatile("barrier.cluster.arrive.relaxed.aligned; barrier.cluster.wait.aligned;" ::: "memory"); }
__device__ __forceinline__ void bar_sync(int id, int n) { asm volatile("bar.sync %0, %1;" :: "r"(id), "r"(n) : "memory"); }
__device__ __forceinline__ void bar_arrive(int id, int n) { asm volatile("bar.arrive %0, %1;" :: "r"(id), "r"(n) : "memory"); }
__device__ __forceinline__ void tma2d(uint32_t dst, const CUtensorMap* m, int c0, int c1, uint32_t bar) {
    asm volatile("cp.async.bulk.tensor.2d.shared::cluster.global.mbarrier::complete_tx::bytes [%0], [%1, {%3, %4}], [%2];"
                 :: "r"(dst), "l"(m), "r"(bar), "r"(c0), "r"(c1) : "memory");
}
__device__ __forceinline__ void tma3d(uint32_t dst, const CUtensorMap* m, int c0, int c1, int c2, uint32_t bar) {
    asm volatile("cp.async.bulk.tensor.3d.shared::cluster.global.mbarrier::complete_tx::bytes [%0], [%1, {%3, %4, %5}], [%2];"
                 :: "r"(dst), "l"(m), "r"(bar), "r"(c0), "r"(c1), "r"(c2) : "memory");
}
__device__ __forceinline__ void tma3d_mc(uint32_t dst, const CUtensorMap* m, int c0, int c1, int c2, uint32_t bar, uint16_t mask) {
    asm volatile("cp.async.bulk.tensor.3d.shared::cluster.global.mbarrier::complete_tx::bytes.multicast::cluster [%0], [%1, {%3, %4, %5}], [%2], %6;"
                 :: "r"(dst), "l"(m), "r"(bar), "r"(c0), "r"(c1), "r"(c2), "h"(mask) : "memory");
}
__device__ __forceinline__ void bulk_g2s(uint32_t dst, const void* src, uint32_t bytes, uint32_t bar) {
    asm volatile("cp.async.bulk.shared::cluster.global.mbarrier::complete_tx::bytes [%0], [%1], %2, [%3];"
                 :: "r"(dst), "l"(src), "r"(bytes), "r"(bar) : "memory");
}
__device__ __forceinline__ void bulk_s2g(void* dst, uint32_t src, uint32_t bytes) {
    asm volatile("cp.async.bulk.global.shared::cta.bulk_group [%0], [%1], %2;" :: "l"(dst), "r"(src), "r"(bytes) : "memory");
}
__device__ __forceinline__ void bulk_commit_wait() { asm volatile("cp.async.bulk.commit_group; cp.async.bulk.wait_group.read 0;" ::: "memory"); }
__device__ __forceinline__ void bulk_commit_wait_all() { asm volatile("cp.async.bulk.commit_group; cp.async.bulk.wait_group 0;" ::: "memory"); }
__device__ __forceinline__ void signal(int c) { asm volatile("red.release.gpu.global.add.u32 [%0], 1;" :: "l"(g_cnt + c * 32) : "memory"); }
__device__ __forceinline__ void signal_done(int c) { asm volatile("red.relaxed.gpu.global.add.u32 [%0], 1;" :: "l"(g_cnt + c * 32) : "memory"); }
__device__ __forceinline__ uint32_t peek(int c) { uint32_t v; asm volatile("ld.relaxed.gpu.global.u32 %0, [%1];" : "=r"(v) : "l"(g_cnt + c * 32) : "memory"); return v; }
__device__ __forceinline__ void await(int c, uint32_t target, uint32_t seen = 0) {
    asm volatile("{\n.reg .pred p;\n.reg .u32 i, v;\nmov.u32 v, %2;\nmov.u32 i, 0;\nA_LOOP:\nsetp.ge.u32 p, v, %1;\n@p bra.uni A_DONE;\n"
                 "ld.relaxed.gpu.global.u32 v, [%0];\nadd.u32 i, i, 1;\nsetp.lt.u32 p, i, 4194304;\n@p bra.uni A_LOOP;\ntrap;\nA_DONE:\nfence.acquire.gpu;\n}"
                 :: "l"(g_cnt + c * 32), "r"(target), "r"(seen) : "memory");
}
#define ELECT "{.reg .pred e; elect.sync _|e, 0xffffffff; @e "
__device__ __forceinline__ void e_signal(int c) { asm volatile(ELECT "red.release.gpu.global.add.u32 [%0], 1;}" :: "l"(g_cnt + c * 32) : "memory"); }
__device__ __forceinline__ void e_arrive(uint32_t bar) { asm volatile(ELECT "mbarrier.arrive.shared::cta.b64 _, [%0];}" :: "r"(bar) : "memory"); }
__device__ __forceinline__ void e_expect(uint32_t bar, uint32_t bytes) { asm volatile(ELECT "mbarrier.arrive.expect_tx.shared::cta.b64 _, [%0], %1;}" :: "r"(bar), "r"(bytes) : "memory"); }
__device__ __forceinline__ void e_tma3d(uint32_t dst, const CUtensorMap* m, int c0, int c1, int c2, uint32_t bar) {
    asm volatile(ELECT "cp.async.bulk.tensor.3d.shared::cluster.global.mbarrier::complete_tx::bytes [%0], [%1, {%3, %4, %5}], [%2];}"
                 :: "r"(dst), "l"(m), "r"(bar), "r"(c0), "r"(c1), "r"(c2) : "memory");
}
__device__ __forceinline__ void e_tma2d(uint32_t dst, const CUtensorMap* m, int c0, int c1, uint32_t bar) {
    asm volatile(ELECT "cp.async.bulk.tensor.2d.shared::cluster.global.mbarrier::complete_tx::bytes [%0], [%1, {%3, %4}], [%2];}"
                 :: "r"(dst), "l"(m), "r"(bar), "r"(c0), "r"(c1) : "memory");
}
__device__ __forceinline__ void e_tma3d_mc(uint32_t dst, const CUtensorMap* m, int c0, int c1, int c2, uint32_t bar) {
    asm volatile(ELECT "cp.async.bulk.tensor.3d.shared::cluster.global.mbarrier::complete_tx::bytes.multicast::cluster [%0], [%1, {%3, %4, %5}], [%2], %6;}"
                 :: "r"(dst), "l"(m), "r"(bar), "r"(c0), "r"(c1), "r"(c2), "h"((uint16_t)3) : "memory");
}
__device__ __forceinline__ void arrive_both(uint32_t bar) {
    asm volatile("{.reg .pred p; .reg .b32 l, ra; mov.u32 l, %laneid; setp.lt.u32 p, l, 2; @p mapa.shared::cluster.u32 ra, %0, l;"
                 "@p mbarrier.arrive.shared::cluster.b64 _, [ra];}" :: "r"(bar) : "memory");
}
__device__ __forceinline__ void e_g2s(uint32_t dst, const void* src, uint32_t bytes, uint32_t bar) {
    asm volatile(ELECT "cp.async.bulk.shared::cluster.global.mbarrier::complete_tx::bytes [%0], [%1], %2, [%3];}"
                 :: "r"(dst), "l"(src), "r"(bytes), "r"(bar) : "memory");
}
template <int N>
__device__ __forceinline__ void kv_load(uint32_t sb, uint32_t bar, int t0, int extra = 0) {
    e_expect(bar, N * 6144 + extra);
    e_g2s(sb + t0 * 6144, g_KV + t0 * 6144, N * 6144, bar);
}
__device__ __forceinline__ void fence_async_all() { asm volatile("fence.proxy.async.global;" ::: "memory"); }
__device__ __forceinline__ void wg_fence() { asm volatile("wgmma.fence.sync.aligned;" ::: "memory"); }
__device__ __forceinline__ void wg_commit() { asm volatile("wgmma.commit_group.sync.aligned;" ::: "memory"); }
template <int N> __device__ __forceinline__ void wg_wait() { asm volatile("wgmma.wait_group.sync.aligned %0;" :: "n"(N) : "memory"); }
template <int N> __device__ __forceinline__ void fence_regs(float (&d)[N]) {
#pragma unroll
    for (int i = 0; i < N; i++) asm volatile("" : "+f"(d[i]) :: "memory");
}
template <int N> __device__ __forceinline__ void fence_regs(uint32_t (&d)[N]) {
#pragma unroll
    for (int i = 0; i < N; i++) asm volatile("" : "+r"(d[i]) :: "memory");
}
template <int N> __device__ __forceinline__ void zero_regs(float (&d)[N]) {
#pragma unroll
    for (int i = 0; i < N; i++) d[i] = 0.f;
    fence_regs(d);
}
__device__ __forceinline__ uint32_t pack_bf16(float lo, float hi) { uint32_t r; asm("cvt.rn.bf16x2.f32 %0, %1, %2;" : "=r"(r) : "f"(hi), "f"(lo)); return r; }
__device__ __forceinline__ float bf_lo(uint32_t v) { return __uint_as_float(v << 16); }
__device__ __forceinline__ float bf_hi(uint32_t v) { return __uint_as_float(v & 0xFFFF0000u); }
__device__ __forceinline__ float ex2(float x) { float r; asm("ex2.approx.ftz.f32 %0, %1;" : "=f"(r) : "f"(x)); return r; }
__device__ __forceinline__ float rcp(float x) { float r; asm("rcp.approx.ftz.f32 %0, %1;" : "=f"(r) : "f"(x)); return r; }
__device__ __forceinline__ void sts32(uint32_t a, uint32_t v) { asm volatile("st.shared.b32 [%0], %1;" :: "r"(a), "r"(v) : "memory"); }
__device__ __forceinline__ void sts64(uint32_t a, uint32_t v0, uint32_t v1) { asm volatile("st.shared.v2.b32 [%0], {%1, %2};" :: "r"(a), "r"(v0), "r"(v1) : "memory"); }
__device__ __forceinline__ void sts128(uint32_t a, uint4 v) { asm volatile("st.shared.v4.b32 [%0], {%1, %2, %3, %4};" :: "r"(a), "r"(v.x), "r"(v.y), "r"(v.z), "r"(v.w) : "memory"); }
__device__ __forceinline__ uint4 lds128(uint32_t a) { uint4 v; asm volatile("ld.shared.v4.b32 {%0, %1, %2, %3}, [%4];" : "=r"(v.x), "=r"(v.y), "=r"(v.z), "=r"(v.w) : "r"(a) : "memory"); return v; }
__device__ __forceinline__ void stsm4(uint32_t a, uint32_t r0, uint32_t r1, uint32_t r2, uint32_t r3) {
    asm volatile("stmatrix.sync.aligned.m8n8.x4.shared.b16 [%0], {%1, %2, %3, %4};" :: "r"(a), "r"(r0), "r"(r1), "r"(r2), "r"(r3) : "memory");
}
__device__ __forceinline__ void ldsm4(uint32_t a, uint32_t& r0, uint32_t& r1, uint32_t& r2, uint32_t& r3) {
    asm volatile("ldmatrix.sync.aligned.m8n8.x4.shared.b16 {%0, %1, %2, %3}, [%4];" : "=r"(r0), "=r"(r1), "=r"(r2), "=r"(r3) : "r"(a) : "memory");
}
__device__ __forceinline__ void ldsm4t(uint32_t a, uint32_t& r0, uint32_t& r1, uint32_t& r2, uint32_t& r3) {
    asm volatile("ldmatrix.sync.aligned.m8n8.x4.trans.shared.b16 {%0, %1, %2, %3}, [%4];" : "=r"(r0), "=r"(r1), "=r"(r2), "=r"(r3) : "r"(a) : "memory");
}
__device__ __forceinline__ void mma16816(float (&d)[4], uint32_t a0, uint32_t a1, uint32_t a2, uint32_t a3, uint32_t b0, uint32_t b1) {
    asm volatile("mma.sync.aligned.m16n8k16.row.col.f32.bf16.bf16.f32 {%0,%1,%2,%3}, {%4,%5,%6,%7}, {%8,%9}, {%0,%1,%2,%3};"
                 : "+f"(d[0]), "+f"(d[1]), "+f"(d[2]), "+f"(d[3]) : "r"(a0), "r"(a1), "r"(a2), "r"(a3), "r"(b0), "r"(b1));
}
__device__ __forceinline__ uint64_t mkdesc(uint32_t addr, uint32_t lbo, uint32_t sbo, uint32_t swz) {
    return (uint64_t)(((addr & 0x3FFFF) >> 4) | ((lbo >> 4) << 16)) | ((uint64_t)((sbo >> 4) | (swz << 30)) << 32);
}
__device__ __forceinline__ float phi(float t, float log2e = 1.4426950408889634f) { return fmaxf(t + 1e-6f, 1e-6f) + fminf(ex2(t * log2e), 1.f); }

__device__ __forceinline__ void finish() {
    if (atomicAdd(g_cnt + C_DONE * 32, 1) == 131)
        for (int i = 0; i < C_N; i++) g_cnt[i * 32] = 0;
}

constexpr int K1_STAGE = 57344, K2_Q = 196608, K2_ZERO = K2_Q + 24576, K3_STAGE = 46080, BARS = 230400, SMEM = BARS + 1280;
enum { B_KV = 0, B_FULL3 = 24, B_EMPTY3 = 64, B_FREE = 88, B_SIDE = 112, B_O1 = 120, B_FULL = 128, B_EMPTY = 208, B_DRAIN = 288, B_MDONE = 296,
       B_EFREE = 304, B_GO = 312, B_END = 320, S_MUL = 336, S_Q2 = 344, S_STAT = 384 };
#define BUNROLL 4
#define ROLL1 1
#define ROLL3 1
constexpr int bunroll = BUNROLL, roll1 = ROLL1, roll3 = ROLL3;
#define K3_BR(b) (((b) >> 3) & 1)

#define PROF_SMEM 0
#define STAMP0()
#define STAMP(k, s)
#define FLUSH()

__device__ __forceinline__ void wg_ss160_acc(float (&d)[80], uint64_t da, uint64_t db) {
  asm volatile("wgmma.mma_async.sync.aligned.m64n160k16.f32.bf16.bf16 "
    "{%0,%1,%2,%3,%4,%5,%6,%7,%8,%9,%10,%11,%12,%13,%14,%15,%16,%17,%18,%19,%20,%21,%22,%23,%24,%25,%26,%27,%28,%29,%30,%31,%32,%33,%34,%35,%36,%37,%38,%39,%40,%41,%42,%43,%44,%45,%46,%47,%48,%49,%50,%51,%52,%53,%54,%55,%56,%57,%58,%59,%60,%61,%62,%63,%64,%65,%66,%67,%68,%69,%70,%71,%72,%73,%74,%75,%76,%77,%78,%79}, "
    "%80, %81, 1, 1, 1, 0, 1;\n"
    : "+f"(d[0]),"+f"(d[1]),"+f"(d[2]),"+f"(d[3]),"+f"(d[4]),"+f"(d[5]),"+f"(d[6]),"+f"(d[7]),"+f"(d[8]),"+f"(d[9]),"+f"(d[10]),"+f"(d[11]),"+f"(d[12]),"+f"(d[13]),"+f"(d[14]),"+f"(d[15]),"+f"(d[16]),"+f"(d[17]),"+f"(d[18]),"+f"(d[19]),"+f"(d[20]),"+f"(d[21]),"+f"(d[22]),"+f"(d[23]),"+f"(d[24]),"+f"(d[25]),"+f"(d[26]),"+f"(d[27]),"+f"(d[28]),"+f"(d[29]),"+f"(d[30]),"+f"(d[31]),"+f"(d[32]),"+f"(d[33]),"+f"(d[34]),"+f"(d[35]),"+f"(d[36]),"+f"(d[37]),"+f"(d[38]),"+f"(d[39]),"+f"(d[40]),"+f"(d[41]),"+f"(d[42]),"+f"(d[43]),"+f"(d[44]),"+f"(d[45]),"+f"(d[46]),"+f"(d[47]),"+f"(d[48]),"+f"(d[49]),"+f"(d[50]),"+f"(d[51]),"+f"(d[52]),"+f"(d[53]),"+f"(d[54]),"+f"(d[55]),"+f"(d[56]),"+f"(d[57]),"+f"(d[58]),"+f"(d[59]),"+f"(d[60]),"+f"(d[61]),"+f"(d[62]),"+f"(d[63]),"+f"(d[64]),"+f"(d[65]),"+f"(d[66]),"+f"(d[67]),"+f"(d[68]),"+f"(d[69]),"+f"(d[70]),"+f"(d[71]),"+f"(d[72]),"+f"(d[73]),"+f"(d[74]),"+f"(d[75]),"+f"(d[76]),"+f"(d[77]),"+f"(d[78]),"+f"(d[79])
    : "l"(da), "l"(db));
}
__device__ __forceinline__ void wg_ss48_acc(float (&d)[24], uint64_t da, uint64_t db) {
  asm volatile("wgmma.mma_async.sync.aligned.m64n48k16.f32.bf16.bf16 "
    "{%0,%1,%2,%3,%4,%5,%6,%7,%8,%9,%10,%11,%12,%13,%14,%15,%16,%17,%18,%19,%20,%21,%22,%23}, "
    "%24, %25, 1, 1, 1, 0, 1;\n"
    : "+f"(d[0]),"+f"(d[1]),"+f"(d[2]),"+f"(d[3]),"+f"(d[4]),"+f"(d[5]),"+f"(d[6]),"+f"(d[7]),"+f"(d[8]),"+f"(d[9]),"+f"(d[10]),"+f"(d[11]),"+f"(d[12]),"+f"(d[13]),"+f"(d[14]),"+f"(d[15]),"+f"(d[16]),"+f"(d[17]),"+f"(d[18]),"+f"(d[19]),"+f"(d[20]),"+f"(d[21]),"+f"(d[22]),"+f"(d[23])
    : "l"(da), "l"(db));
}
__device__ __forceinline__ void wg_tt96_acc(float (&d)[48], uint64_t da, uint64_t db) {
  asm volatile("wgmma.mma_async.sync.aligned.m64n96k16.f32.bf16.bf16 "
    "{%0,%1,%2,%3,%4,%5,%6,%7,%8,%9,%10,%11,%12,%13,%14,%15,%16,%17,%18,%19,%20,%21,%22,%23,%24,%25,%26,%27,%28,%29,%30,%31,%32,%33,%34,%35,%36,%37,%38,%39,%40,%41,%42,%43,%44,%45,%46,%47}, "
    "%48, %49, 1, 1, 1, 1, 1;\n"
    : "+f"(d[0]),"+f"(d[1]),"+f"(d[2]),"+f"(d[3]),"+f"(d[4]),"+f"(d[5]),"+f"(d[6]),"+f"(d[7]),"+f"(d[8]),"+f"(d[9]),"+f"(d[10]),"+f"(d[11]),"+f"(d[12]),"+f"(d[13]),"+f"(d[14]),"+f"(d[15]),"+f"(d[16]),"+f"(d[17]),"+f"(d[18]),"+f"(d[19]),"+f"(d[20]),"+f"(d[21]),"+f"(d[22]),"+f"(d[23]),"+f"(d[24]),"+f"(d[25]),"+f"(d[26]),"+f"(d[27]),"+f"(d[28]),"+f"(d[29]),"+f"(d[30]),"+f"(d[31]),"+f"(d[32]),"+f"(d[33]),"+f"(d[34]),"+f"(d[35]),"+f"(d[36]),"+f"(d[37]),"+f"(d[38]),"+f"(d[39]),"+f"(d[40]),"+f"(d[41]),"+f"(d[42]),"+f"(d[43]),"+f"(d[44]),"+f"(d[45]),"+f"(d[46]),"+f"(d[47])
    : "l"(da), "l"(db));
}
__device__ __forceinline__ void wg_tt48_acc(float (&d)[24], uint64_t da, uint64_t db) {
  asm volatile("wgmma.mma_async.sync.aligned.m64n48k16.f32.bf16.bf16 "
    "{%0,%1,%2,%3,%4,%5,%6,%7,%8,%9,%10,%11,%12,%13,%14,%15,%16,%17,%18,%19,%20,%21,%22,%23}, "
    "%24, %25, 1, 1, 1, 1, 1;\n"
    : "+f"(d[0]),"+f"(d[1]),"+f"(d[2]),"+f"(d[3]),"+f"(d[4]),"+f"(d[5]),"+f"(d[6]),"+f"(d[7]),"+f"(d[8]),"+f"(d[9]),"+f"(d[10]),"+f"(d[11]),"+f"(d[12]),"+f"(d[13]),"+f"(d[14]),"+f"(d[15]),"+f"(d[16]),"+f"(d[17]),"+f"(d[18]),"+f"(d[19]),"+f"(d[20]),"+f"(d[21]),"+f"(d[22]),"+f"(d[23])
    : "l"(da), "l"(db));
}
__device__ __forceinline__ void wg_qk64_new(float (&d)[32], uint64_t da, uint64_t db) {
  asm volatile("wgmma.mma_async.sync.aligned.m64n64k16.f32.bf16.bf16 "
    "{%0,%1,%2,%3,%4,%5,%6,%7,%8,%9,%10,%11,%12,%13,%14,%15,%16,%17,%18,%19,%20,%21,%22,%23,%24,%25,%26,%27,%28,%29,%30,%31}, "
    "%32, %33, 0, 1, 1, 0, 0;\n"
    : "=f"(d[0]),"=f"(d[1]),"=f"(d[2]),"=f"(d[3]),"=f"(d[4]),"=f"(d[5]),"=f"(d[6]),"=f"(d[7]),"=f"(d[8]),"=f"(d[9]),"=f"(d[10]),"=f"(d[11]),"=f"(d[12]),"=f"(d[13]),"=f"(d[14]),"=f"(d[15]),"=f"(d[16]),"=f"(d[17]),"=f"(d[18]),"=f"(d[19]),"=f"(d[20]),"=f"(d[21]),"=f"(d[22]),"=f"(d[23]),"=f"(d[24]),"=f"(d[25]),"=f"(d[26]),"=f"(d[27]),"=f"(d[28]),"=f"(d[29]),"=f"(d[30]),"=f"(d[31])
    : "l"(da), "l"(db));
}
__device__ __forceinline__ void wg_qk64_acc(float (&d)[32], uint64_t da, uint64_t db) {
  asm volatile("wgmma.mma_async.sync.aligned.m64n64k16.f32.bf16.bf16 "
    "{%0,%1,%2,%3,%4,%5,%6,%7,%8,%9,%10,%11,%12,%13,%14,%15,%16,%17,%18,%19,%20,%21,%22,%23,%24,%25,%26,%27,%28,%29,%30,%31}, "
    "%32, %33, 1, 1, 1, 0, 0;\n"
    : "+f"(d[0]),"+f"(d[1]),"+f"(d[2]),"+f"(d[3]),"+f"(d[4]),"+f"(d[5]),"+f"(d[6]),"+f"(d[7]),"+f"(d[8]),"+f"(d[9]),"+f"(d[10]),"+f"(d[11]),"+f"(d[12]),"+f"(d[13]),"+f"(d[14]),"+f"(d[15]),"+f"(d[16]),"+f"(d[17]),"+f"(d[18]),"+f"(d[19]),"+f"(d[20]),"+f"(d[21]),"+f"(d[22]),"+f"(d[23]),"+f"(d[24]),"+f"(d[25]),"+f"(d[26]),"+f"(d[27]),"+f"(d[28]),"+f"(d[29]),"+f"(d[30]),"+f"(d[31])
    : "l"(da), "l"(db));
}
__device__ __forceinline__ void wg_pv24_acc(float (&d)[12], uint32_t a0, uint32_t a1, uint32_t a2, uint32_t a3, uint64_t db) {
  asm volatile("wgmma.mma_async.sync.aligned.m64n24k16.f32.bf16.bf16 "
    "{%0,%1,%2,%3,%4,%5,%6,%7,%8,%9,%10,%11}, "
    "{%12,%13,%14,%15}, %16, 1, 1, 1, 1;\n"
    : "+f"(d[0]),"+f"(d[1]),"+f"(d[2]),"+f"(d[3]),"+f"(d[4]),"+f"(d[5]),"+f"(d[6]),"+f"(d[7]),"+f"(d[8]),"+f"(d[9]),"+f"(d[10]),"+f"(d[11])
    : "r"(a0), "r"(a1), "r"(a2), "r"(a3), "l"(db));
}
__device__ __forceinline__ void wg_rs160_acc(float (&d)[80], uint32_t a0, uint32_t a1, uint32_t a2, uint32_t a3, uint64_t db) {
  asm volatile("wgmma.mma_async.sync.aligned.m64n160k16.f32.bf16.bf16 "
    "{%0,%1,%2,%3,%4,%5,%6,%7,%8,%9,%10,%11,%12,%13,%14,%15,%16,%17,%18,%19,%20,%21,%22,%23,%24,%25,%26,%27,%28,%29,%30,%31,%32,%33,%34,%35,%36,%37,%38,%39,%40,%41,%42,%43,%44,%45,%46,%47,%48,%49,%50,%51,%52,%53,%54,%55,%56,%57,%58,%59,%60,%61,%62,%63,%64,%65,%66,%67,%68,%69,%70,%71,%72,%73,%74,%75,%76,%77,%78,%79}, "
    "{%80,%81,%82,%83}, %84, 1, 1, 1, 1;\n"
    : "+f"(d[0]),"+f"(d[1]),"+f"(d[2]),"+f"(d[3]),"+f"(d[4]),"+f"(d[5]),"+f"(d[6]),"+f"(d[7]),"+f"(d[8]),"+f"(d[9]),"+f"(d[10]),"+f"(d[11]),"+f"(d[12]),"+f"(d[13]),"+f"(d[14]),"+f"(d[15]),"+f"(d[16]),"+f"(d[17]),"+f"(d[18]),"+f"(d[19]),"+f"(d[20]),"+f"(d[21]),"+f"(d[22]),"+f"(d[23]),"+f"(d[24]),"+f"(d[25]),"+f"(d[26]),"+f"(d[27]),"+f"(d[28]),"+f"(d[29]),"+f"(d[30]),"+f"(d[31]),"+f"(d[32]),"+f"(d[33]),"+f"(d[34]),"+f"(d[35]),"+f"(d[36]),"+f"(d[37]),"+f"(d[38]),"+f"(d[39]),"+f"(d[40]),"+f"(d[41]),"+f"(d[42]),"+f"(d[43]),"+f"(d[44]),"+f"(d[45]),"+f"(d[46]),"+f"(d[47]),"+f"(d[48]),"+f"(d[49]),"+f"(d[50]),"+f"(d[51]),"+f"(d[52]),"+f"(d[53]),"+f"(d[54]),"+f"(d[55]),"+f"(d[56]),"+f"(d[57]),"+f"(d[58]),"+f"(d[59]),"+f"(d[60]),"+f"(d[61]),"+f"(d[62]),"+f"(d[63]),"+f"(d[64]),"+f"(d[65]),"+f"(d[66]),"+f"(d[67]),"+f"(d[68]),"+f"(d[69]),"+f"(d[70]),"+f"(d[71]),"+f"(d[72]),"+f"(d[73]),"+f"(d[74]),"+f"(d[75]),"+f"(d[76]),"+f"(d[77]),"+f"(d[78]),"+f"(d[79])
    : "r"(a0), "r"(a1), "r"(a2), "r"(a3), "l"(db));
}

template <int BS>
__device__ __forceinline__ void stage8heads(const float (&acc)[80], uint32_t base, int c) {
    const uint32_t la = base + 4 * c;
    const uint32_t lc = base + (c < 2 ? 2 * BS + 4 * c : 3 * BS + 4 * c - 8);
    const uint32_t ld = base + 3 * BS + (c < 2 ? 8 + 4 * c : BS - 8 + 4 * c);
#pragma unroll
    for (int p = 0; p < 4; p++) {
#pragma unroll
        for (int jj = 0; jj < 5; jj++) {
            const uint32_t a = (jj < 2 ? la + jj * BS : jj == 2 ? lc : ld + (jj - 3) * BS) + p * 6 * BS;
            sts32(a, pack_bf16(acc[20 * p + 4 * jj], acc[20 * p + 4 * jj + 1]));
            sts32(a + 128, pack_bf16(acc[20 * p + 4 * jj + 2], acc[20 * p + 4 * jj + 3]));
        }
    }
}

template <int PHI>
__device__ __forceinline__ void store_q(const float (&acc)[80], uint32_t sa, uint32_t reg, uint8_t* dst, int lane, uint32_t kaddr) {
    float k;
#pragma unroll
    for (int j = 0; j < 20; j += 2) {
        if (j == 0 || j == 10) asm volatile("ld.volatile.shared.f32 %0, [%1];" : "=f"(k) : "r"(kaddr) : "memory");
        float v[8];
#pragma unroll
        for (int i = 0; i < 8; i++) v[i] = PHI ? phi(acc[4 * j + i], k) : acc[4 * j + i] * k;
        stsm4(sa + j * 256, pack_bf16(v[0], v[1]), pack_bf16(v[2], v[3]), pack_bf16(v[4], v[5]), pack_bf16(v[6], v[7]));
        if (j == 8 || j == 18) {
            fence_async_smem();
            __syncwarp();
            if (lane == 0) bulk_s2g(dst + (j - 8) * 256, reg + (j - 8) * 256, 2560);
        }
    }
}

__device__ __forceinline__ uint32_t exp_mufu(float a, float b) { return pack_bf16(ex2(a), ex2(b)); }
__device__ __forceinline__ uint32_t exp_soft(float a, float b, uint32_t c64k) {
    uint32_t y, m, e;
    asm("mad.lo.u32 %0, %1, %2, %3;" : "=r"(y) : "r"(__float_as_uint(b)), "r"(c64k), "r"(__float_as_uint(a)));
    asm("lop3.b32 %0, %1, 0x007F007F, 0x3F803F80, 0xEA;" : "=r"(m) : "r"(y));
    asm("fma.rn.bf16x2 %0, %1, %1, %2;" : "=r"(e) : "r"(m), "r"(0x40014001));
    return e + y - m;
}
__device__ __forceinline__ void do_exps(const float (&s)[32], uint32_t (&p)[16], uint32_t c64k) {
#pragma unroll
    for (int i = 0; i < 16; i++) p[i] = ((i >> 1) & 3) == 1 ? exp_mufu(s[2 * i], s[2 * i + 1]) : exp_soft(s[2 * i], s[2 * i + 1], c64k);
}
__device__ __forceinline__ void qk64(float (&s)[32], uint64_t q1, uint64_t q2, uint64_t kd) {
    wg_qk64_new(s, q1, kd + (64 << 16));
    wg_qk64_acc(s, q2, kd + 128);
}
__device__ __forceinline__ void pv64(float (&o)[12], const uint32_t (&p)[16], uint64_t kd) {
#pragma unroll
    for (int j = 0; j < 4; j++) wg_pv24_acc(o, p[4 * j], p[4 * j + 1], p[4 * j + 2], p[4 * j + 3], kd + 192 + j * 48 + (24 << 16));
}
struct OAddr { uint8_t* even; uint8_t* odd; };
__device__ __forceinline__ OAddr o_addr(int qt, int hg, int row, int c) {
    uint8_t* base = g_A + ((qt >> 1) * 80 + hg * 20) * 2048 + ((qt & 1) * 64 + row) * 16;
    return {base + 4 * c, base + 4096 + (c < 2 ? 8 + 4 * c : 2040 + 4 * c)};
}
__device__ __forceinline__ void store_o(const float (&o)[12], const OAddr& a, int t, int lane) {
    const float i0 = rcp(__shfl_sync(0xffffffffu, o[8], (lane & 28) | 2)), i1 = rcp(__shfl_sync(0xffffffffu, o[10], (lane & 28) | 2));
    uint8_t* p = ((t & 1) ? a.odd : a.even) + (t >> 1) * 10240;
#pragma unroll
    for (int j = 0; j < 3; j++) {
        if (j < 2 || (lane & 2) == 0) {
            *(uint32_t*)(p + j * 2048) = pack_bf16(o[4 * j] * i0, o[4 * j + 1] * i0);
            *(uint32_t*)(p + j * 2048 + 128) = pack_bf16(o[4 * j + 2] * i1, o[4 * j + 3] * i1);
        }
    }
}

__device__ __forceinline__ void attn_fallback(uint32_t sb, int qt, int hg, int warp, int lane) {
    const int g = lane >> 2, c = lane & 3;
    for (int i = 0; i < 3; i++) mbar_wait(sb + BARS + B_KV + 8 * i, 0);
    for (int u = warp; u < 32; u += 16) {
        const int t = u >> 2, sl = u & 3;
        uint32_t a0, a1, a2, a3, a4, a5, x0, x1;
        const uint32_t qa = sb + K2_Q + t * 3072 + (sl * 16 + (lane & 15)) * 16;
        ldsm4(qa + (lane >> 4) * 1024, a0, a1, a2, a3);
        ldsm4(qa + 2048, a4, a5, x0, x1);
        if (c >= 2) { a4 = 0; a5 = 0; }
        float m0 = -INFINITY, m1 = -INFINITY;
        float o[12];
#pragma unroll
        for (int i = 0; i < 12; i++) o[i] = 0.f;
#pragma unroll 1
        for (int st = 0; st < 32; st++) {
            const uint32_t kb = sb + st * 6144;
            float s[8][4];
#pragma unroll
            for (int j = 0; j < 8; j++) {
                uint32_t b0, b1, b2, b3;
                const int mi = lane >> 3;
                ldsm4(kb + (mi < 3 ? mi : 2) * 1024 + (j * 8 + (lane & 7)) * 16, b0, b1, b2, b3);
                s[j][0] = s[j][1] = s[j][2] = s[j][3] = 0.f;
                mma16816(s[j], a0, a1, a2, a3, b0, b1);
                mma16816(s[j], a4, a5, 0u, 0u, b2, b2);
            }
            float n0 = m0, n1 = m1;
#pragma unroll
            for (int j = 0; j < 8; j++) { n0 = fmaxf(n0, fmaxf(s[j][0], s[j][1])); n1 = fmaxf(n1, fmaxf(s[j][2], s[j][3])); }
            n0 = fmaxf(n0, __shfl_xor_sync(0xffffffffu, n0, 1)); n0 = fmaxf(n0, __shfl_xor_sync(0xffffffffu, n0, 2));
            n1 = fmaxf(n1, __shfl_xor_sync(0xffffffffu, n1, 1)); n1 = fmaxf(n1, __shfl_xor_sync(0xffffffffu, n1, 2));
            const float r0 = ex2(m0 - n0), r1 = ex2(m1 - n1);
            m0 = n0; m1 = n1;
#pragma unroll
            for (int j = 0; j < 3; j++) { o[4 * j] *= r0; o[4 * j + 1] *= r0; o[4 * j + 2] *= r1; o[4 * j + 3] *= r1; }
#pragma unroll
            for (int kk = 0; kk < 4; kk++) {
                const uint32_t p0 = exp_mufu(s[2 * kk][0] - m0, s[2 * kk][1] - m0), p1 = exp_mufu(s[2 * kk][2] - m1, s[2 * kk][3] - m1);
                const uint32_t p2 = exp_mufu(s[2 * kk + 1][0] - m0, s[2 * kk + 1][1] - m0), p3 = exp_mufu(s[2 * kk + 1][2] - m1, s[2 * kk + 1][3] - m1);
                uint32_t b0, b1, b2, b3, b4, b5, y0, y1;
                const uint32_t va = kb + 3072 + (2 * kk + ((lane >> 3) & 1)) * 384 + (lane & 7) * 16;
                ldsm4t(va + (lane >> 4) * 128, b0, b1, b2, b3);
                ldsm4t(va + 256, b4, b5, y0, y1);
                float (&o4)[3][4] = *reinterpret_cast<float (*)[3][4]>(o);
                mma16816(o4[0], p0, p1, p2, p3, b0, b1);
                mma16816(o4[1], p0, p1, p2, p3, b2, b3);
                mma16816(o4[2], p0, p1, p2, p3, b4, b5);
            }
        }
        store_o(o, o_addr(qt, hg, sl * 16 + g, c), t, lane);
    }
}

__device__ __forceinline__ void load5(uint4 (&u)[5], const uint8_t* src) {
#pragma unroll
    for (int i = 0; i < 5; i++) u[i] = __ldcg((const uint4*)(src + i * 256));
}
__device__ __forceinline__ void side_jobs(const uint32_t sb, int hg, const bf16* __restrict__ wo, int tid, int warp, int lane) {
    const uint32_t bar = sb + BARS + B_SIDE, kvs = sb + 207360, zs = sb + 227840;
    if (tid == 0) mbar_expect(bar, 160 * 1280);
    fence_async_smem();
    __syncthreads();
    for (int i = tid; i < 8 * 2560 / 16; i += 512) sts128(kvs + i * 16, make_uint4(0, 0, 0, 0));
    if (tid < 160) bulk_g2s(sb + tid * 1296, wo + (hg * 160 + tid) * 640, 1280, bar);
    if (warp == 15) await(C_B, 96);
    __syncthreads();
    STAMP(1, 1);
#pragma unroll 1
    for (int i = tid; i < 1120; i += 512) {
        const bool z = i >= 960;
        const float4* src = z ? (const float4*)g_zp + (i - 960) : (const float4*)(g_kvp + hg * 8 * 480) + i;
        const int step = z ? 160 : 32 * 120;
        float4 a = make_float4(0.f, 0.f, 0.f, 0.f);
        float4 v[16];
#pragma unroll
        for (int r = 0; r < 16; r++) v[r] = __ldcg(src + r * step);
#pragma unroll
        for (int r = 0; r < 16; r++) { a.x += v[r].x; a.y += v[r].y; a.z += v[r].z; a.w += v[r].w; }
        const int h = i / 120, rem = i - h * 120, d = rem / 6, e = (rem - d * 6) * 4;
        if (z) sts128(zs + (i - 960) * 16, make_uint4(__float_as_uint(a.x), __float_as_uint(a.y), __float_as_uint(a.z), __float_as_uint(a.w)));
        else if (e < 20) sts64(kvs + h * 2560 + d * 80 + e * 2, pack_bf16(a.x, a.y), pack_bf16(a.z, a.w));
    }
    __syncthreads();
    mbar_wait(bar, 0);
    STAMP(1, 2);
    const int g = lane >> 2, c = lane & 3;
#pragma unroll 1
    for (int u = warp; u < 64; u += 16) {
        const int h = u >> 3, nc = u & 7;
        uint32_t a[2][2][4];
#pragma unroll
        for (int mt = 0; mt < 2; mt++)
#pragma unroll
            for (int ks = 0; ks < 2; ks++)
                ldsm4(kvs + h * 2560 + (mt * 16 + (lane & 15)) * 80 + (ks * 16 + (lane >> 4) * 8) * 2, a[mt][ks][0], a[mt][ks][1], a[mt][ks][2], a[mt][ks][3]);
        const uint32_t wr = sb + (h * 20 + min(lane, 19)) * 1296 + nc * 160, out = sb + (h * 20 + g) * 1296 + nc * 160 + 4 * c;
#pragma unroll 2
        for (int nb = 0; nb < 10; nb++) {
            uint32_t b0, b1, b2, b3;
            ldsm4t(wr + nb * 16, b0, b1, b2, b3);
            float d0[4] = {0.f, 0.f, 0.f, 0.f}, d1[4] = {0.f, 0.f, 0.f, 0.f};
            mma16816(d0, a[0][0][0], a[0][0][1], a[0][0][2], a[0][0][3], b0, b1);
            mma16816(d0, a[0][1][0], a[0][1][1], a[0][1][2], a[0][1][3], b2, b3);
            mma16816(d1, a[1][0][0], a[1][0][1], a[1][0][2], a[1][0][3], b0, b1);
            mma16816(d1, a[1][1][0], a[1][1][1], a[1][1][2], a[1][1][3], b2, b3);
            sts32(out + nb * 16, pack_bf16(d0[0], d0[1]));
            sts32(out + nb * 16 + 8 * 1296, pack_bf16(d0[2], d0[3]));
            if (g < 4) sts32(out + nb * 16 + 16 * 1296, pack_bf16(d1[0], d1[1]));
        }
        fence_async_smem();
        __syncthreads();
        const int row = (u >> 4) * 40 + lane * 16 + warp;
        if (lane * 16 + warp < 40) bulk_s2g(g_M + (hg * 160 + row) * 640, sb + row * 1296, 1280);
    }
    STAMP(1, 3);
    const int pr = (warp & 7) * 2 + (lane >> 4), r = lane & 15, sl0 = hg * 32 + (warp >> 3);
    const uint8_t* src = g_Q + ((128 + sl0) * 80 + pr * 5) * 256 + r * 16;
    uint4 un[2][5], z[10];
    load5(un[0], src);
    load5(un[1], src + 40960);
#pragma unroll
    for (int i = 0; i < 10; i++) z[i] = lds128(zs + pr * 160 + i * 16);
    if (lane < 3) bulk_commit_wait_all();
    __syncthreads();
    if (tid == 0) signal_done(C_M);
    STAMP(1, 4);
#pragma unroll 1
    for (int it = 0; it < 16; it += 2) {
#pragma unroll
        for (int h = 0; h < 2; h++) {
            float den[2] = {1e-6f, 1e-6f};
#pragma unroll
            for (int i = 0; i < 10; i++) {
                const uint32_t u0 = i & 1 ? un[h][i >> 1].z : un[h][i >> 1].x, u1 = i & 1 ? un[h][i >> 1].w : un[h][i >> 1].y;
                den[i / 5] = fmaf(bf_hi(u1), __uint_as_float(z[i].w), fmaf(bf_lo(u1), __uint_as_float(z[i].z),
                             fmaf(bf_hi(u0), __uint_as_float(z[i].y), fmaf(bf_lo(u0), __uint_as_float(z[i].x), den[i / 5]))));
            }
            if (it < 14) load5(un[h], src + (it + h + 2) * 40960);
            const float r0 = rcp(den[0]), r1 = rcp(den[1]);
            *(uint2*)(g_F + (sl0 + 2 * (it + h)) * 512 + (warp & 7) * 64 + r * 4 + (lane >> 4) * 2) = make_uint2(pack_bf16(r0, r0), pack_bf16(r1, r1));
        }
    }
    __syncthreads();
    if (tid == 0) { signal(C_F); finish(); }
}
struct Maps { CUtensorMap xA, xB, wq, wqkv, wo, M, Q, O; };
__device__ __forceinline__ void k3_load(uint32_t sb, const Maps& mp, int n, int br, int rt, int ct, bool w, bool a) {
    const int s = n < 5 ? n : n - 5, e = br ? n : n < 4 ? 2 * n : 2 * n - 7;
    const uint32_t st = sb + s * K3_STAGE, bar = sb + BARS + B_FULL3 + 8 * s;
    if (w) {
        e_expect(bar, K3_STAGE);
        if (((n ^ rt) & 1) == 0) e_tma3d_mc(st + 20480, br ? &mp.M : &mp.wo, 0, e * 80, ct * 5, bar);
    }
    if (a) {
        if (br) e_tma3d(st, &mp.Q, 0, rt * 8, e * 10, bar);
        else e_g2s(st, g_A + rt * 163840 + e * 20480, 20480, bar);
    }
}
__device__ __forceinline__ int k3_flag(int e, int br, int rt) { return br ? (e == 0 ? C_M : C_F) : C_O1 + rt; }
__device__ __forceinline__ void k3_early(uint32_t sb, const Maps& mp, int e, int br, int rt, int ct, uint32_t seen = 0) {
    if (br ? e == 0 || e == 3 : e == 1) await(k3_flag(e, br, rt), br ? 4 : 8, seen);
    if (e == 3) { e_arrive(sb + BARS + B_GO); return; }
    mbar_wait(sb + BARS + B_FREE + 8 * e, 0);
    fence_async_all();
    k3_load(sb, mp, e, br, rt, ct, true, br || e);
    if (!br && e == 1) k3_load(sb, mp, 0, 0, rt, ct, false, true);
}
template <int KS>
__device__ __forceinline__ void scale_x(uint32_t (&x)[20], uint32_t la, const uint4& u, const uint4& v, bool hi) {
    ldsm4(la + KS * 4096, x[4 * KS], x[4 * KS + 1], x[4 * KS + 2], x[4 * KS + 3]);
#pragma unroll
    for (int i = 4 * KS; i < 4 * KS + 4; i++) {
        const int j = i >> 1;
        const uint4& f = (i & 1) ? v : u;
        const uint32_t m = j < 2 ? f.x : j == 2 ? (hi ? f.y : f.x) : j < 5 ? f.y : j < 7 ? f.z : j == 7 ? (hi ? f.w : f.z) : f.w;
        asm("mul.rn.bf16x2 %0, %0, %1;" : "+r"(x[i]) : "r"(m));
    }
}
__device__ __forceinline__ void b_step(float (&acc)[80], uint32_t (&x)[20], uint32_t (&y)[20], int n, uint32_t sb, uint32_t la, uint64_t db,
                                       const uint4& u, const uint4& v, bool hi, bool lead, bool first) {
    const int s = n < 5 ? n : n - 5, t = n < 4 ? n + 1 : n - 4;
    const uint64_t d = db + s * (K3_STAGE >> 4);
    la += t * K3_STAGE;
    fence_regs(x);
    wg_fence();
#pragma unroll
    for (int ks = 0; ks < 5; ks++) wg_rs160_acc(acc, x[4 * ks], x[4 * ks + 1], x[4 * ks + 2], x[4 * ks + 3], d + ks * 64);
    wg_commit();
    if (n == 0 && first) bar_arrive(2, 256);
    wg_wait<1>();
    fence_regs(y);
    if (n >= 1 && n <= 3 && lead) arrive_both(sb + BARS + B_EMPTY3 + 8 * (n - 1));
    if (n < 7) mbar_wait(sb + BARS + B_FULL3 + 8 * t, n >= 4);
    if (n == 1) STAMP(2, 1);
    if (n == 2) STAMP(2, 6);
    if (n == 3) STAMP(2, 7);
    scale_x<0>(y, la, u, v, hi); scale_x<1>(y, la, u, v, hi); scale_x<2>(y, la, u, v, hi); scale_x<3>(y, la, u, v, hi); scale_x<4>(y, la, u, v, hi);
}
__device__ __forceinline__ uint32_t sq2(uint32_t a, uint32_t n) { uint32_t r; asm("fma.rn.bf16x2 %0, %1, %1, %2;" : "=r"(r) : "r"(a), "r"(n)); return r; }
#define SETREG(op, n) asm volatile("setmaxnreg." #op ".sync.aligned.u32 " #n ";")

__global__ void __cluster_dims__(2, 1, 1) __launch_bounds__(512, 1)
fused(const __grid_constant__ Maps mp, const bf16* __restrict__ wk, const bf16* __restrict__ wv, const bf16* __restrict__ woA,
      const bf16* __restrict__ woB, uint32_t c64k) {
    extern __shared__ __align__(1024) uint8_t smem[];
    const uint32_t sb = __reduce_max_sync(0xffffffffu, smem_u32(smem)), bars = sb + BARS;
    const int tid = threadIdx.x, lane = tid & 31, b = blockIdx.x;
    const int warp = __reduce_max_sync(0xffffffffu, tid >> 5);
    const bool spare = b >= 128;
    const int qt = b >> 2, hg = b & 3;
    const int br3 = K3_BR(b), rt3 = (b >> 4) * 2 + (b & 1), ct3 = (b >> 1) & 3;
    STAMP0();
    {
    const uint32_t full = bars + B_FULL, empty = bars + B_EMPTY, drain = bars + B_DRAIN;
    const int ct = (b >> 1) & 7, rt = ((b >> 4) << 1) | (b & 1), rank = b & 1, sp = b - 128;
    const CUtensorMap* mx = (ct < 2 || spare) ? &mp.xA : &mp.xB;
    const CUtensorMap* mw = ct < 2 ? &mp.wq : &mp.wqkv;
    const int grp0 = ct < 4 ? 10 * (ct & 1) : 5 * ct, gstep = ct < 4 ? 5 : 20;
    if (tid == 256) {
        mbar_init(full, 1);
        fence_async_smem();
        if (!spare) {
            mbar_expect(full, K1_STAGE);
            tma2d(sb, mx, 0, rt * 128, full);
            tma3d(sb + 16384, mw, 0, 0, grp0, full);
            tma3d(sb + 36864, mw, 0, 0, grp0 + gstep, full);
        }
        for (int s = 0; s < 10; s++) { if (s) mbar_init(full + 8 * s, 1); mbar_init(empty + 8 * s, spare ? 2 : 4); }
        fence_mbar_init();
        if (spare) {
            fence_async_smem();
#pragma unroll 1
            for (int s = 0; s < 10; s++) { mbar_expect(full + 8 * s, 16384); tma2d(sb + s * 16384, mx, s * 64, sp * 512, full + 8 * s); }
        }
    } else if (tid == 288) {
        mbar_init(drain, 2); mbar_init(bars + B_MDONE, 2); mbar_init(bars + B_EFREE, 8); mbar_init(bars + B_SIDE, 1); mbar_init(bars + B_GO, 1); mbar_init(bars + B_END, 2); mbar_init(bars + B_O1, 16);
        for (int s = 0; s < 5; s++) mbar_init(bars + B_FULL3 + 8 * s, 1);
        for (int s = 0; s < 3; s++) { mbar_init(bars + B_KV + 8 * s, 1); mbar_init(bars + B_EMPTY3 + 8 * s, 4); mbar_init(bars + B_FREE + 8 * s, 8); }
        sts32(bars + S_MUL, __float_as_uint(ct < 2 ? QSCALE : 1.4426950408889634f));
        fence_mbar_init();
        fence_async_smem();
    }
    if (spare) {
#pragma unroll 1
        for (int r = tid; r < 1280; r += 512) {
            const int m = r >= 640;
            const uint32_t d = sb + 163840 + m * (30720 - 10240) + r * 16;
            const bf16* src = (m ? wv : wk) + (r - 640 * m) * 20;
#pragma unroll
            for (int j = 0; j < 5; j++) asm volatile("cp.async.ca.shared.global [%0], [%1], 8;" :: "r"(d + (j >> 1) * 10240 + (j & 1) * 8), "l"(src + 4 * j) : "memory");
            sts64(d + 20488, 0u, 0u);
        }
    }
    __syncwarp();
    cluster_sync();
    const int g = lane >> 2, c = lane & 3;
    if (spare) {
        const uint32_t wb = sb + 163840;
        asm volatile("cp.async.wait_all;" ::: "memory");
        STAMP(0, 1);
        fence_async_smem();
        __syncthreads();
        if (warp == 8) {
#pragma unroll 1
            for (int i = 10; i < 40; i++) {
                const int rb = i / 10, s = i - rb * 10;
                mbar_wait(empty + 8 * s, (rb - 1) & 1);
                e_expect(full + 8 * s, 16384);
                e_tma2d(sb + s * 16384, mx, s * 64, sp * 512 + rb * 128, full + 8 * s);
            }
        }
        __syncwarp();
        const int w4 = warp & 3, hf2 = warp >> 2;
        const uint64_t da = mkdesc(sb + hf2 * 8192, 16, 1024, 1), db = mkdesc(wb, 128, 10240, 0);
        uint32_t kmax = 0, vmax = 0;
#pragma unroll 1
        for (int rb = warp < 8 ? 0 : 4; rb < 4; rb++) {
            float acc[24];
            if (rb == 0) STAMP(0, 2);
            if (rb == 1) STAMP(0, 4);
            zero_regs(acc);
#pragma unroll 1
            for (int s = 0; s < 10; s++) {
                mbar_wait(full + 8 * s, rb & 1);
                const uint64_t xa = da + (uint32_t)(s * 1024), xb = db + (uint32_t)(s * 64);
                wg_fence();
#pragma unroll
                for (int ks = 0; ks < 4; ks++) wg_ss48_acc(acc, xa + ks * 2, xb + ks * 16);
                wg_commit();
                wg_wait<1>();
                if (s >= 1 && w4 == 0) e_arrive(empty + 8 * (s - 1));
                __syncwarp();
            }
            wg_wait<0>();
            fence_regs(acc);
            if (rb == 0) STAMP(0, 3);
            if (w4 == 0) e_arrive(empty + 72);
            uint8_t* img = g_KV + (sp * 8 + rb * 2 + hf2) * 6144;
#pragma unroll
            for (int hf = 0; hf < 2; hf++) {
                const int key = w4 * 16 + g + 8 * hf;
                uint32_t kk[3], vv[3];
#pragma unroll
                for (int j = 0; j < 3; j++) {
                    kk[j] = pack_bf16(acc[4 * j + 2 * hf], acc[4 * j + 2 * hf + 1]);
                    vv[j] = pack_bf16(acc[12 + 4 * j + 2 * hf], acc[12 + 4 * j + 2 * hf + 1]);
                }
                float n2 = 0.f;
#pragma unroll
                for (int j = 0; j < 3; j++) {
                    n2 = fmaf(bf_lo(kk[j]), bf_lo(kk[j]), n2); n2 = fmaf(bf_hi(kk[j]), bf_hi(kk[j]), n2);
                    vmax = max(vmax, max((vv[j] << 16) & 0x7FFFFFFFu, vv[j] & 0x7FFF0000u));
                }
                n2 += __shfl_xor_sync(0xffffffffu, n2, 1);
                n2 += __shfl_xor_sync(0xffffffffu, n2, 2);
                kmax = max(kmax, __float_as_uint(n2) & 0x7FFFFFFFu);
                if (c == 2) { kk[2] = ((key >> 3) & 3) == 1 ? MUFU_OFF : (key & 1) ? 0xC18447C0u : 0x42FE47C0u; vv[2] = 0x00003F80u; }
#pragma unroll
                for (int j = 0; j < 3; j++) {
                    *(uint32_t*)(img + j * 1024 + key * 16 + 4 * c) = kk[j];
                    *(uint32_t*)(img + 3072 + (key >> 3) * 384 + j * 128 + (key & 7) * 16 + 4 * c) = vv[j];
                }
            }
        }
        kmax = __reduce_max_sync(0xffffffffu, kmax);
        vmax = __reduce_max_sync(0xffffffffu, vmax);
        STAMP(0, 5);
        if (lane == 0 && warp < 8) { g_stat[sp * 8 + warp] = kmax; g_stat[32 + sp * 8 + warp] = vmax; }
        __syncthreads();
        if (tid == 0) signal(C_KV);
        STAMP(0, 7);
        side_jobs(sb, sp, woB, tid, warp, lane);
        STAMP(1, 7); FLUSH();
        return;
    }
    if (warp >= 8) {
        SETREG(dec, 48);
        if (tid == 256) {
#pragma unroll 1
            for (int kb = 1; kb < 10; kb++) {
                const int s = kb & 3;
                if (kb >= 4) mbar_wait(empty + 8 * s, (kb >> 2) - 1);
                else if (kb >= 2) mbar_wait(full + 8 * (kb - 2), 0);
                mbar_expect(full + 8 * s, K1_STAGE);
                tma2d(sb + s * K1_STAGE, mx, kb * 64, rt * 128, full + 8 * s);
                tma3d_mc(sb + s * K1_STAGE + 16384 + rank * 20480, mw, 0, kb * 64, grp0 + rank * gstep, full + 8 * s, 3);
            }
        }
        __syncwarp();
        mbar_wait(bars + B_MDONE, 0);
        {
            const uint32_t kvb = bars + B_KV;
            if (warp == 12) {
                await(C_KV, 4);
                fence_async_all();
                kv_load<6>(sb, kvb, 0, 256);
                e_g2s(bars + S_STAT, g_stat, 256, kvb);
                kv_load<12>(sb, kvb + 8, 6);
            }
            if (tid == 320) asm volatile("cp.async.bulk.prefetch.L2.global [%0], 6400;" :: "l"(woA + b * 3200) : "memory");
            STAMP(1, 0);
            const int pr = (warp - 8) >> 1, r = (warp & 1) * 32 + lane;
            await(C_Q + qt * 2 + (hg >> 1), 4);
            STAMP(1, 1);
            uint4 u[5];
            load5(u, g_Q + ((qt * 4 + (r >> 4)) * 80 + hg * 20 + pr * 5) * 256 + (r & 15) * 16);
            if (ct >= 4) mbar_wait(bars + B_EFREE, 0);
            if (warp >= 14) sts128(sb + K2_ZERO + (tid - 448) * 16, make_uint4(0, 0, 0, 0));
            const uint32_t d = sb + K2_Q + pr * 6144 + r * 16;
            sts128(d, u[0]);
            sts128(d + 1024, u[1]);
            sts128(d + 2048, make_uint4(u[2].x, u[2].y, 0x3F803F80u, 0u));
            sts128(d + 3072, make_uint4(u[2].z, u[2].w, u[3].x, u[3].y));
            sts128(d + 4096, make_uint4(u[3].z, u[3].w, u[4].x, u[4].y));
            sts128(d + 5120, make_uint4(u[4].z, u[4].w, 0x3F803F80u, 0u));
            fence_async_smem();
            STAMP(1, 2);
            const uint32_t n0 = sq2(u[2].y, sq2(u[2].x, sq2(u[1].w, sq2(u[1].z, sq2(u[1].y, sq2(u[1].x, sq2(u[0].w, sq2(u[0].z, sq2(u[0].y, sq2(u[0].x, 0))))))))));
            const uint32_t n1 = sq2(u[2].z, sq2(u[2].w, sq2(u[3].x, sq2(u[3].y, sq2(u[3].z, sq2(u[3].w, sq2(u[4].x, sq2(u[4].y, sq2(u[4].z, sq2(u[4].w, 0))))))))));
            const uint32_t q2 = __reduce_max_sync(0xffffffffu, max(__float_as_uint(bf_lo(n0) + bf_hi(n0)) & 0x7FFFFFFFu, __float_as_uint(bf_lo(n1) + bf_hi(n1)) & 0x7FFFFFFFu));
            if (lane == 0) sts32(bars + S_Q2 + (warp - 8) * 4, q2);
            __syncwarp();
            STAMP(1, 3);
        }
        SETREG(inc, 128);
    } else {
    SETREG(inc, 208);
    {
        const int wg = warp >> 2, w4 = warp & 3;
        float acc0[80], acc1[80];
        zero_regs(acc0); zero_regs(acc1);
        const uint64_t da = mkdesc(sb + wg * 8192, 16, 1024, 1), db = mkdesc(sb + 16384, 4096, 512, 2);
#pragma unroll roll1
        for (int kb = 0; kb < 10; kb++) {
            const int s = kb & 3;
            mbar_wait(full + 8 * s, (kb >> 2) & 1);
            if (kb == 0) STAMP(0, 1);
            if (kb == 4) STAMP(0, 2);
            const uint64_t xa = da + (uint32_t)(s * (K1_STAGE >> 4)), xb = db + (uint32_t)(s * (K1_STAGE >> 4));
            wg_fence();
#pragma unroll
            for (int ks = 0; ks < 4; ks++) {
                wg_ss160_acc(acc0, xa + ks * 2, xb + ks * 64);
                wg_ss160_acc(acc1, xa + ks * 2, xb + 1280 + ks * 64);
            }
            wg_commit();
            wg_wait<1>();
            if (w4 == 0) {
                if (kb >= 1 && kb <= 6) arrive_both(empty + 8 * ((kb - 1) & 3));
                if (kb == 8) e_arrive(drain);
            }
            __syncwarp();
        }
        wg_wait<0>();
        fence_regs(acc0); fence_regs(acc1);
        STAMP(0, 3);
        if (w4 == 0) e_arrive(bars + B_MDONE);
        mbar_wait(drain, 0);
        const int row = w4 * 16 + g;
        if (ct < 4) {
            const uint32_t reg = sb + 2 * K1_STAGE + warp * 10240, sa = reg + (lane >> 4) * 256 + (lane & 15) * 16;
            uint8_t* dst = g_Q + (((ct >> 1) * 128 + rt * 8 + warp) * 80 + (ct & 1) * 40) * 256;
            if (ct < 2) { store_q<0>(acc0, sa, reg, dst, lane, bars + S_MUL); store_q<0>(acc1, sa + 5120, reg + 5120, dst + 5120, lane, bars + S_MUL); }
            else { store_q<1>(acc0, sa, reg, dst, lane, bars + S_MUL); store_q<1>(acc1, sa + 5120, reg + 5120, dst + 5120, lane, bars + S_MUL); }
            STAMP(0, 4);
            if (lane == 0) {
                bulk_commit_wait();
                asm volatile("cp.async.bulk.wait_group 0;" ::: "memory");
                if (ct < 2) signal_done(C_Q + (rt * 2 + wg) * 2 + ct);
            }
            if (ct >= 2) { bar_sync(1, 256); if (tid == 0) signal_done(C_B); }
            STAMP(0, 5);
        } else {
            const uint32_t pk = sb + 2 * K1_STAGE, vv = pk + 49152;
            const uint32_t sa = pk + (lane >> 4) * 2048 + (wg * 64 + w4 * 16 + (lane & 15)) * 16;
#pragma unroll
            for (int j = 0; j < 20; j += 2)
                stsm4(sa + j * 2048, pack_bf16(phi(acc0[4 * j]), phi(acc0[4 * j + 1])), pack_bf16(phi(acc0[4 * j + 2]), phi(acc0[4 * j + 3])),
                      pack_bf16(phi(acc0[4 * j + 4]), phi(acc0[4 * j + 5])), pack_bf16(phi(acc0[4 * j + 6]), phi(acc0[4 * j + 7])));
            stage8heads<2048>(acc1, vv + (wg * 64 + row) * 16, c);
#pragma unroll
            for (int i = 0; i < 4; i++) sts64(vv + (2 * i + (tid >> 7)) * 6144 + 4096 + (tid & 127) * 16 + 8, 0x00003F80u, 0u);
            fence_async_smem();
            bar_sync(1, 256);
            STAMP(0, 4);
            const uint64_t dk = mkdesc(pk, 128, 2048, 0), dv = mkdesc(vv, 128, 2048, 0);
            float* kvp = g_kvp + (rt * 32 + (ct - 4) * 8) * 480;
            float* zp = g_zp + rt * 640 + (ct - 4) * 160;
            float t0[48], t2[24];
            zero_regs(t0); zero_regs(t2);
            wg_fence();
            const uint64_t dk0 = dk + wg * ((8 * 2048) >> 4), dv0 = dv + wg * ((9 * 2048) >> 4);
#pragma unroll
            for (int ks = 0; ks < 8; ks++) wg_tt96_acc(t0, dk0 + ks * 16, dv0 + ks * 16);
            wg_commit();
            wg_wait<0>();
            fence_regs(t0);
            if (wg == 0) {
                wg_fence();
#pragma unroll
                for (int ks = 0; ks < 8; ks++) wg_tt48_acc(t2, dk + ((16 * 2048) >> 4) + ks * 16, dv + ((18 * 2048) >> 4) + ks * 16);
                wg_commit();
                wg_wait<0>();
                fence_regs(t2);
            }
            if (lane == 0) mbar_arrive(bars + B_EFREE);
#pragma unroll
            for (int hf = 0; hf < 2; hf++) {
                const int m = wg * 64 + row + 8 * hf, hm = m / 20, d = m - hm * 20;
#pragma unroll
                for (int j = 0; j < 12; j++) {
                    if (hm == wg * 3 + j / 3) {
                        *(float2*)(kvp + hm * 480 + d * 24 + (j % 3) * 8 + 2 * c) = make_float2(t0[4 * j + 2 * hf], t0[4 * j + 2 * hf + 1]);
                        if (j % 3 == 2 && c == 2) zp[m] = t0[4 * j + 2 * hf];
                    }
                }
                if (wg == 0) {
                    const int m2 = 128 + row + 8 * hf, h2 = m2 / 20, d2 = m2 - h2 * 20;
#pragma unroll
                    for (int j = 0; j < 6; j++) {
                        if (h2 == 6 + j / 3) {
                            *(float2*)(kvp + h2 * 480 + d2 * 24 + (j % 3) * 8 + 2 * c) = make_float2(t2[4 * j + 2 * hf], t2[4 * j + 2 * hf + 1]);
                            if (j % 3 == 2 && c == 2) zp[m2] = t2[4 * j + 2 * hf];
                        }
                    }
                }
            }
            bar_sync(1, 256);
            if (tid == 0) signal(C_B);
            STAMP(0, 5);
        }
    }
    SETREG(dec, 128);
    }
    }
    __syncthreads();
    uint32_t q2, k2, vm;
    mbar_wait(bars + B_KV, 0);
    asm volatile("ld.shared.u32 %0, [%1];" : "=r"(q2) : "r"(bars + S_Q2 + (lane & 7) * 4) : "memory");
    asm volatile("ld.shared.u32 %0, [%1];" : "=r"(k2) : "r"(bars + S_STAT + lane * 4) : "memory");
    asm volatile("ld.shared.u32 %0, [%1];" : "=r"(vm) : "r"(bars + S_STAT + 128 + lane * 4) : "memory");
    q2 = __reduce_max_sync(0xffffffffu, q2);
    const bool slow = __reduce_or_sync(0xffffffffu, !(__uint_as_float(q2) * __uint_as_float(k2) <= SAFE_BOUND * SAFE_BOUND / 1.05f && __uint_as_float(vm) <= 1e18f));
    if (slow) {
        if (warp == 0) kv_load<14>(sb, bars + B_KV + 16, 18);
        attn_fallback(sb, qt, hg, warp, lane);
        __syncthreads();
        if ((warp & 3) == 0) { arrive_both(bars + B_FREE); arrive_both(bars + B_FREE + 8); arrive_both(bars + B_FREE + 16); }
        if (warp == 8) {
            e_signal(C_O1 + (qt >> 1));
#pragma unroll 1
            for (int e = 0; e < 4; e++) k3_early(sb, mp, e, br3, rt3, ct3);
        }
    } else {
    float o[12], sa[32], sc[32];
    uint32_t p[16];
    zero_regs(o);
    const uint32_t kb32 = (uint32_t)mkdesc(sb, 0, 128, 0);
#define D64(lo) ((uint64_t)(lo) | (8ull << 32))
    const uint32_t qa = (uint32_t)mkdesc(sb + K2_Q, 1024, 0, 0) + (warp >> 2) * 192;
    const uint32_t qb = (uint32_t)mkdesc(sb + K2_Q + 2048, K2_ZERO - K2_Q - 2048, 0, 0) + (warp >> 2) * (192 - (192 << 16));
    uint64_t q1 = D64(qa), q2d = D64(qb);
    uint64_t ka = D64(kb32);
    int it = 0;
    uint32_t seen = 0;
    const uint32_t todo = 0x10110 | ((warp & 3) ? 0 : 0x5400 | (warp ? 0x200 << (warp >> 1) : 0x8000));
    if (warp == 12) kv_load<14>(sb, bars + B_KV + 16, 18);
    mbar_wait(bars + B_KV + 8, 0);
    STAMP(1, 4);
    wg_fence();
    qk64(sa, q1, q2d, ka);
    wg_commit();
    qk64(sc, q1, q2d, ka + 384);
    wg_commit();
    wg_wait<1>();
    fence_regs(sa);
#define STEP(x, y, kv, a1, a2, kq) do_exps(x, p, c64k); fence_regs(p); wg_fence(); pv64(o, p, kv); wg_commit(); qk64(x, a1, a2, kq); wg_commit(); \
                                   wg_wait<1>(); fence_regs(y); fence_regs(p)
#pragma unroll 1
    while (true) {
        it++;
        const uint64_t n1 = D64((uint32_t)q1 + (it == 8 ? 768 : 0)), n2 = D64((uint32_t)q2d + (it == 8 ? 768 - (768 << 16) : 0));
        const uint64_t kn = D64(it == 8 ? kb32 : (uint32_t)ka + 1536);
        STEP(sa, sc, ka, q1, q2d, ka + 768);
        STEP(sc, sa, ka + 384, q1, q2d, ka + 1152);
        STEP(sa, sc, ka + 768, n1, n2, kn);
        STEP(sc, sa, ka + 1152, n1, n2, kn + 384);
        fence_regs(o);
        ka = kn; q1 = n1; q2d = n2;
        if ((todo >> it) & 1) {
            if (it == 16) break;
            const int wg = warp >> 2;
            if (it == 4) mbar_wait(bars + B_KV + 16, 0);
            if (it == 8) {
                STAMP(1, 7);
                int tl;
                asm volatile("mov.u32 %0, %tid.x;" : "=r"(tl));
                store_o(o, o_addr(qt, hg, ((tl >> 5) & 3) * 16 + ((tl & 31) >> 2), tl & 3), wg, tl & 31);
                zero_regs(o);
                __syncwarp();
                e_arrive(bars + B_O1);
            }
            if (it == 10 && warp == 0) { mbar_wait(bars + B_O1, 0); e_signal(C_O1 + (qt >> 1)); }
            if ((warp & 3) == 0 && it >= 10) {
                const int e = (wg - 1) & 3, at = wg ? 9 + 2 * wg : 15;
                if (!(it & 1)) {
                    arrive_both(bars + B_FREE + 4 * (it - 10));
                    if (it == at - 1) seen = peek(k3_flag(e, br3, rt3));
                } else if (it == at) k3_early(sb, mp, e, br3, rt3, ct3, seen);
            }
            __syncwarp();
        }
    }
    STAMP(1, 5);
    store_o(o, o_addr(qt, hg, (warp & 3) * 16 + (lane >> 2), lane & 3), 4 + (warp >> 2), lane);
    wg_wait<0>();
    fence_regs(sc);
    }
    uint4 f[6];
    const uint4* F = (const uint4*)g_F + (rt3 * 8 + warp) * 128 + (lane >> 2);
    if (br3 && warp < 8) {
        mbar_wait(bars + B_GO, 0);
#pragma unroll
        for (int i = 0; i < 6; i++) f[i] = __ldcg(F + i * 8);
    }
    STAMP(1, 6);
    __syncthreads();
    const uint32_t full = bars + B_FULL3, empty = bars + B_EMPTY3;
    if (warp >= 8) {
        if (br3) SETREG(dec, 40);
        if (warp == 12) e_signal(C_O2 + (qt >> 1));
        if (warp == 8) {
            arrive_both(bars + B_END);
            k3_load(sb, mp, 3, br3, rt3, ct3, false, true);
            mbar_wait(bars + B_END, 0);
            k3_load(sb, mp, 3, br3, rt3, ct3, true, false);
            k3_load(sb, mp, 4, br3, rt3, ct3, true, br3);
            if (!br3) {
                await(C_O2 + rt3, 8);
                fence_async_all();
                k3_load(sb, mp, 4, 0, rt3, ct3, false, true);
            }
            STAMP(2, 1);
#pragma unroll 1
            for (int n = 5; n < 8; n++) {
                mbar_wait(empty + 8 * (n - 5), 0);
                k3_load(sb, mp, n, br3, rt3, ct3, true, true);
            }
            if (lane == 0) finish();
        }
        FLUSH();
        return;
    }
    STAMP(2, 0);
    const int wg = warp >> 2, w4 = warp & 3;
    float acc[80];
    const uint64_t db = mkdesc(sb + 20480, 5120, 512, 2);
    zero_regs(acc);
    if (br3) {
        SETREG(inc, 216);
        const uint32_t la = sb + (lane >> 4) * 2048 + (warp * 16 + (lane & 15)) * 16;
        const bool hi = lane & 2;
        uint32_t x[20], y[20];
        mbar_wait(full, 0);
        STAMP(2, 2);
        scale_x<0>(x, la, f[0], f[1], hi); scale_x<1>(x, la, f[0], f[1], hi); scale_x<2>(x, la, f[0], f[1], hi);
        scale_x<3>(x, la, f[0], f[1], hi); scale_x<4>(x, la, f[0], f[1], hi);
        if (wg == 1) bar_sync(2, 256);
#pragma unroll bunroll
        for (int n = 0; n < 8; n += 2) {
            uint4 h[4];
#pragma unroll
            for (int i = 0; i < 4; i++) h[i] = __ldcg(F + min(2 * n + 6 + i, 15) * 8);
            if (n == 4) STAMP(2, 3);
            b_step(acc, x, y, n, sb, la, db, f[2], f[3], hi, w4 == 0, wg == 0);
            b_step(acc, y, x, n + 1, sb, la, db, f[4], f[5], hi, w4 == 0, false);
#pragma unroll
            for (int i = 0; i < 4; i++) f[2 + i] = h[i];
        }
    } else {
        const uint64_t da = mkdesc(sb + wg * 1024, 2048, 128, 0);
#pragma unroll roll3
        for (int n = 0; n < 8; n++) {
            const int s = n < 5 ? n : n - 5;
            mbar_wait(full + 8 * s, n >= 5);
            if (n == 0) STAMP(2, 2);
            if (n == 4) STAMP(2, 3);
            const uint64_t xa = da + (uint32_t)(s * (K3_STAGE >> 4)), xb = db + (uint32_t)(s * (K3_STAGE >> 4));
            wg_fence();
#pragma unroll
            for (int ks = 0; ks < 5; ks++) wg_ss160_acc(acc, xa + ks * 256, xb + ks * 64);
            wg_commit();
            wg_wait<1>();
            if (n >= 1 && n <= 3 && w4 == 0) arrive_both(empty + 8 * (n - 1));
            __syncwarp();
        }
    }
    wg_wait<0>();
    fence_regs(acc);
    STAMP(2, 4);
    const uint32_t reg = sb + 3 * K3_STAGE + warp * 5120, sa = reg + (lane & 15) * 160 + (lane >> 4) * 16;
    bar_sync(1, 256);
#pragma unroll
    for (int j = 0; j < 20; j += 2) {
        stsm4(sa + (j < 10 ? j * 16 : 2560 + (j - 10) * 16), pack_bf16(acc[4 * j], acc[4 * j + 1]), pack_bf16(acc[4 * j + 2], acc[4 * j + 3]),
              pack_bf16(acc[4 * j + 4], acc[4 * j + 5]), pack_bf16(acc[4 * j + 6], acc[4 * j + 7]));
        if (j == 8 || j == 18) {
            fence_async_smem();
            __syncwarp();
            if (lane == 0)
                asm volatile("cp.async.bulk.tensor.2d.global.shared::cta.bulk_group [%0, {%2, %3}], [%1];"
                             :: "l"(&mp.O), "r"(reg + (j - 8) * 256), "r"(br3 * 640 + ct3 * 160 + (j - 8) * 8), "r"(rt3 * 128 + warp * 16) : "memory");
        }
    }
    if (lane == 0) bulk_commit_wait();
    STAMP(2, 5); FLUSH();
}

typedef CUresult (*EncodeFn)(CUtensorMap*, CUtensorMapDataType, cuuint32_t, void*, const cuuint64_t*, const cuuint64_t*, const cuuint32_t*,
                             const cuuint32_t*, CUtensorMapInterleave, CUtensorMapSwizzle, CUtensorMapL2promotion, CUtensorMapFloatOOBfill);

static void map_x(EncodeFn enc, CUtensorMap* m, void* p, int rows) {
    cuuint64_t dims[2] = {640, 2048}, str[1] = {1280};
    cuuint32_t box[2] = {64, (cuuint32_t)rows}, es[2] = {1, 1};
    enc(m, CU_TENSOR_MAP_DATA_TYPE_BFLOAT16, 2, p, dims, str, box, es, CU_TENSOR_MAP_INTERLEAVE_NONE, CU_TENSOR_MAP_SWIZZLE_128B,
        CU_TENSOR_MAP_L2_PROMOTION_L2_256B, CU_TENSOR_MAP_FLOAT_OOB_FILL_NONE);
}
static void map_q(EncodeFn enc, CUtensorMap* m, void* p) {
    cuuint64_t dims[3] = {32, 128, 80}, str[2] = {20480, 256};
    cuuint32_t box[3] = {32, 8, 10}, es[3] = {1, 1, 1};
    enc(m, CU_TENSOR_MAP_DATA_TYPE_FLOAT64, 3, p, dims, str, box, es, CU_TENSOR_MAP_INTERLEAVE_NONE, CU_TENSOR_MAP_SWIZZLE_NONE,
        CU_TENSOR_MAP_L2_PROMOTION_L2_256B, CU_TENSOR_MAP_FLOAT_OOB_FILL_NONE);
}
static void map_o(EncodeFn enc, CUtensorMap* m, void* p) {
    cuuint64_t dims[2] = {1280, 2048}, str[1] = {2560};
    cuuint32_t box[2] = {80, 16}, es[2] = {1, 1};
    enc(m, CU_TENSOR_MAP_DATA_TYPE_BFLOAT16, 2, p, dims, str, box, es, CU_TENSOR_MAP_INTERLEAVE_NONE, CU_TENSOR_MAP_SWIZZLE_NONE,
        CU_TENSOR_MAP_L2_PROMOTION_NONE, CU_TENSOR_MAP_FLOAT_OOB_FILL_NONE);
}
static void map_w(EncodeFn enc, CUtensorMap* m, void* p, int n, int rows) {
    cuuint64_t dims[3] = {32, 640, (cuuint64_t)(n / 32)}, str[2] = {(cuuint64_t)n * 2, 64};
    cuuint32_t box[3] = {32, (cuuint32_t)rows, 5}, es[3] = {1, 1, 1};
    enc(m, CU_TENSOR_MAP_DATA_TYPE_BFLOAT16, 3, p, dims, str, box, es, CU_TENSOR_MAP_INTERLEAVE_NONE, CU_TENSOR_MAP_SWIZZLE_64B,
        CU_TENSOR_MAP_L2_PROMOTION_L2_256B, CU_TENSOR_MAP_FLOAT_OOB_FILL_NONE);
}

extern "C" void kernel_launch(void* const* d_in, const int* in_sizes, int n_in, void* d_out, int out_size) {
    static EncodeFn enc = nullptr;
    static void *pM = nullptr, *pQ = nullptr;
    if (!enc) {
        cudaDriverEntryPointQueryResult qr;
        cudaGetDriverEntryPoint("cuTensorMapEncodeTiled", (void**)&enc, cudaEnableDefault, &qr);
        cudaGetSymbolAddress(&pM, g_M);
        cudaGetSymbolAddress(&pQ, g_Q);
        cudaFuncSetAttribute(fused, cudaFuncAttributeMaxDynamicSharedMemorySize, SMEM + PROF_SMEM);
    }
    Maps mp;
    map_x(enc, &mp.xA, d_in[0], 128); map_x(enc, &mp.xB, d_in[5], 128);
    map_w(enc, &mp.wq, d_in[1], 640, 64); map_w(enc, &mp.wqkv, d_in[6], 1920, 64);
    map_w(enc, &mp.wo, d_in[4], 640, 80); map_w(enc, &mp.M, pM, 640, 80);
    map_q(enc, &mp.Q, (uint8_t*)pQ + 128 * 20480); map_o(enc, &mp.O, d_out);
    fused<<<132, 512, SMEM + PROF_SMEM, cudaStreamPerThread>>>(mp, (const bf16*)d_in[2], (const bf16*)d_in[3], (const bf16*)d_in[4], (const bf16*)d_in[7], 65536u);
}
```
